```python
import torch

def _softmax(x, axis=-1):
    return torch.softmax(x, dim=axis)

def _gelu(x):
    return torch.nn.functional.gelu(x, approximate='tanh')

def _silu(x):
    return torch.nn.functional.silu(x)

def _sigmoid(x):
    return torch.sigmoid(x)

def _layernorm(x, axis=-1, eps=1e-05):
    m = x.mean(dim=axis, keepdim=True)
    v = x.var(dim=axis, keepdim=True, unbiased=False)
    return (x - m) / torch.sqrt(v + eps)

def _scatter_add(tgt, idx, src, axis=0):
    return tgt.clone().index_add_(axis, idx, src)

def _segment_sum(src, seg, n):
    out = torch.zeros((n,) + src.shape[1:], dtype=src.dtype)
    return out.index_add_(0, seg, src)

def _pad(x, pw):
    flat = tuple((v for pair in reversed(pw) for v in pair))
    return torch.nn.functional.pad(x, flat)
kernel_name = 'adaLN_cond__memory_aug_recurrent_mem_tr__moe_arch_mod__prompt'

def setup_inputs():

    _w = lambda a: (lambda t: t.to(torch.bfloat16) if t.is_floating_point() else t)(torch.as_tensor(a))

    def _A_setup():
        B, S, Dm = (1, 2048, 512)
        H, Dh = (32, 128)
        M, seg = (8, 32)
        seg = min(seg, S)
        S = S // seg * seg
        return {'x': _w((lambda *s: torch.randn(*s, dtype=torch.bfloat16) * 0.05)(B, S, Dm)), 'mem0': _w((lambda *s: torch.randn(*s, dtype=torch.bfloat16) * 0.4)(B, M, Dm)), 'Wq': _w((lambda *s: torch.randn(*s, dtype=torch.bfloat16) * 3.2)(Dm, H, Dh) * Dm ** (-0.5)), 'Wk': _w((lambda *s: torch.randn(*s, dtype=torch.bfloat16) * 3.2)(Dm, H, Dh) * Dm ** (-0.5)), 'Wv': _w((lambda *s: torch.randn(*s, dtype=torch.bfloat16) * 0.4)(Dm, H, Dh) * Dm ** (-0.5)), 'Wo': _w((lambda *s: torch.randn(*s, dtype=torch.bfloat16) * 0.4)(H, Dh, Dm) * (H * Dh) ** (-0.5)), 'seg_len': seg}
    _A_in = _A_setup()

    def _B_setup():
        B, S, D, F, C = (1, 2048, 512, 1376, 2)
        return {'x': _w((lambda *s: torch.randn(*s, dtype=torch.bfloat16) * 0.05)(B, S, D)), 'w_r': _w((lambda *s: torch.randn(*s, dtype=torch.bfloat16) * 0.05)(D)), 'w_gate': _w((lambda *s: torch.randn(*s, dtype=torch.bfloat16) * 0.05)(D, F)), 'w_up': _w((lambda *s: torch.randn(*s, dtype=torch.bfloat16) * 0.05)(D, F)), 'w_down': _w((lambda *s: torch.randn(*s, dtype=torch.bfloat16) * 0.05)(F, D))}
    _B_in = _B_setup()
    return {'A_x': _A_in['x'], 'A_mem0': _A_in['mem0'], 'A_Wq': _A_in['Wq'], 'A_Wk': _A_in['Wk'], 'A_Wv': _A_in['Wv'], 'A_Wo': _A_in['Wo'], 'A_seg_len': _A_in['seg_len'], 'B_x': _B_in['x'], 'B_w_r': _B_in['w_r'], 'B_w_gate': _B_in['w_gate'], 'B_w_up': _B_in['w_up'], 'B_w_down': _B_in['w_down'], 'c': _w((lambda *s: torch.randn(*s, dtype=torch.bfloat16) * 0.05)(1, 512) * 8.0), 'w_mod': _w((lambda *s: torch.randn(*s, dtype=torch.bfloat16) * 0.05)(512, 6 * 512) * 512 ** (-0.5) * 8.0)}

def reference(A_x, A_mem0, A_Wq, A_Wk, A_Wv, A_Wo, A_seg_len, B_x, B_w_r, B_w_gate, B_w_up, B_w_down, c, w_mod):

    def _A_ref(x, mem0, Wq, Wk, Wv, Wo, seg_len):
        B, S, Dm = x.shape
        H, Dh = (Wq.shape[1], Wq.shape[2])
        M = mem0.shape[1]
        scale = Dh ** (-0.5)
        n_seg = S // seg_len
        L = M + seg_len
        idx = torch.arange(L)
        mask = (idx[:, None] < M) | (idx[:, None] >= idx[None, :])
        mem = mem0
        outs = []
        for s in range(n_seg):
            xs = x[:, s * seg_len:(s + 1) * seg_len, :].clone()
            h = torch.concatenate([mem, xs], axis=1)
            q = torch.einsum('btd,dhe->bhte', h, Wq)
            k = torch.einsum('btd,dhe->bhte', h, Wk)
            v = torch.einsum('btd,dhe->bhte', h, Wv)
            scores = torch.einsum('bhqe,bhke->bhqk', q, k) * scale
            scores = torch.where(mask[None, None], scores, -1000000000.0)
            p = _softmax(scores, axis=-1)
            o = torch.einsum('bhqk,bhke->bhqe', p, v)
            o = torch.einsum('bhte,hed->btd', o, Wo)
            mem = o[:, :M, :].clone()
            outs.append(o[:, M:, :])
        return torch.concatenate(outs, axis=1)

    def _B_ref(x, w_r, w_gate, w_up, w_down):
        B, S, D = x.shape
        C = 2
        r = x @ w_r
        idx = torch.argsort(-r, axis=-1)[:, :C]
        idx_e = (lambda x, n, axis: torch.repeat_interleave(x, n, dim=axis))(idx.reshape(B, C, 1), D, axis=2)
        x_sel = (lambda x, i, axis: torch.take_along_dim(x, i, dim=axis))(x, idx_e, axis=1)
        g = _silu(x_sel @ w_gate)
        u = x_sel @ w_up
        y = g * u @ w_down
        r_sel = _sigmoid((lambda x, i, axis: torch.take_along_dim(x, i, dim=axis))(r, idx, axis=1))
        y = y * r_sel.reshape(B, C, 1)
        b_off = (torch.arange(B) * S).reshape(B, 1)
        flat_idx = (idx + b_off).reshape(B * C)
        zero = (x * 0.0).reshape(B * S, D)
        upd = _scatter_add(zero, flat_idx, y.reshape(B * C, D), axis=0)
        return x + upd.reshape(B, S, D)
    x = A_x
    mod = (_silu(c) @ w_mod).reshape(c.shape[0], 6, 1, -1)
    sa, ca, ga, sb, cb, gb = (mod[:, 0].clone(), mod[:, 1].clone(), mod[:, 2].clone(), mod[:, 3].clone(), mod[:, 4].clone(), mod[:, 5].clone())
    h = _layernorm(x, axis=-1) * (1 + ca) + sa
    x = x + ga * _A_ref(h, A_mem0, A_Wq, A_Wk, A_Wv, A_Wo, A_seg_len)
    h = _layernorm(x, axis=-1) * (1 + cb) + sb
    x = x + gb * _B_ref(h, B_w_r, B_w_gate, B_w_up, B_w_down)
    return x
```

```cpp
#include <cuda_runtime.h>
#include <cuda_bf16.h>
#include <cuda.h>
#include <stdint.h>
#include <string.h>
typedef __nv_bfloat16 bf16;
__device__ __forceinline__ uint32_t s2u(const void* p){return (uint32_t)__cvta_generic_to_shared(p);}
__device__ __forceinline__ uint32_t mapa(uint32_t a, uint32_t r){uint32_t d; asm("mapa.shared::cluster.u32 %0,%1,%2;":"=r"(d):"r"(a),"r"(r)); return d;}
__device__ __forceinline__ void mbar_init(uint32_t b,uint32_t c){asm volatile("mbarrier.init.shared::cta.b64 [%0],%1;"::"r"(b),"r"(c):"memory");}
__device__ __forceinline__ void mbar_expect(uint32_t b,uint32_t tx){asm volatile("mbarrier.arrive.expect_tx.shared::cta.b64 _,[%0],%1;"::"r"(b),"r"(tx):"memory");}
__device__ __forceinline__ void mbar_arrive(uint32_t b){asm volatile("mbarrier.arrive.shared::cta.b64 _,[%0];"::"r"(b):"memory");}
__device__ __forceinline__ void mbar_wait(uint32_t b,uint32_t par){
  asm volatile("{\n.reg .pred p;\n.reg .u32 n;\nmov.u32 n,0;\nWL:\nmbarrier.try_wait.parity.shared::cta.b64 p,[%0],%1;\n@p bra WD;\nadd.u32 n,n,1;\nsetp.lt.u32 p,n,0x1000000;\n@p bra WL;\ntrap;\nWD:\n}"::"r"(b),"r"(par):"memory");
}
__device__ __forceinline__ void st_async4(uint32_t a,uint32_t v,uint32_t b){asm volatile("st.async.weak.shared::cluster.mbarrier::complete_tx::bytes.b32 [%0],%1,[%2];"::"r"(a),"r"(v),"r"(b):"memory");}
__device__ __forceinline__ void st_async8(uint32_t a,uint32_t v0,uint32_t v1,uint32_t b){asm volatile("st.async.weak.shared::cluster.mbarrier::complete_tx::bytes.v2.b32 [%0],{%1,%2},[%3];"::"r"(a),"r"(v0),"r"(v1),"r"(b):"memory");}
__device__ __forceinline__ void ldsm4(uint32_t (&r)[4],uint32_t a){asm volatile("ldmatrix.sync.aligned.m8n8.x4.shared.b16 {%0,%1,%2,%3},[%4];":"=r"(r[0]),"=r"(r[1]),"=r"(r[2]),"=r"(r[3]):"r"(a):"memory");}
__device__ __forceinline__ void ldsm4t(uint32_t (&r)[4],uint32_t a){asm volatile("ldmatrix.sync.aligned.m8n8.x4.trans.shared.b16 {%0,%1,%2,%3},[%4];":"=r"(r[0]),"=r"(r[1]),"=r"(r[2]),"=r"(r[3]):"r"(a):"memory");}
__device__ __forceinline__ void ldsm2(uint32_t &r0,uint32_t &r1,uint32_t a){asm volatile("ldmatrix.sync.aligned.m8n8.x2.shared.b16 {%0,%1},[%2];":"=r"(r0),"=r"(r1):"r"(a):"memory");}
__device__ __forceinline__ void ldsm2t(uint32_t &r0,uint32_t &r1,uint32_t a){asm volatile("ldmatrix.sync.aligned.m8n8.x2.trans.shared.b16 {%0,%1},[%2];":"=r"(r0),"=r"(r1):"r"(a):"memory");}
__device__ __forceinline__ void stsm4t(uint32_t a,uint32_t r0,uint32_t r1,uint32_t r2,uint32_t r3){asm volatile("stmatrix.sync.aligned.m8n8.x4.trans.shared.b16 [%0],{%1,%2,%3,%4};"::"r"(a),"r"(r0),"r"(r1),"r"(r2),"r"(r3):"memory");}
__device__ __forceinline__ void stsm2t(uint32_t a,uint32_t r0,uint32_t r1){asm volatile("stmatrix.sync.aligned.m8n8.x2.trans.shared.b16 [%0],{%1,%2};"::"r"(a),"r"(r0),"r"(r1):"memory");}
__device__ __forceinline__ void mma16816(float (&c)[4],const uint32_t (&a)[4],uint32_t b0,uint32_t b1){
  asm volatile("mma.sync.aligned.m16n8k16.row.col.f32.bf16.bf16.f32 {%0,%1,%2,%3},{%4,%5,%6,%7},{%8,%9},{%0,%1,%2,%3};"
    :"+f"(c[0]),"+f"(c[1]),"+f"(c[2]),"+f"(c[3]):"r"(a[0]),"r"(a[1]),"r"(a[2]),"r"(a[3]),"r"(b0),"r"(b1));}
__device__ __forceinline__ uint32_t pack2(float lo,float hi){uint32_t r; asm("cvt.rn.bf16x2.f32 %0,%1,%2;":"=r"(r):"f"(hi),"f"(lo)); return r;}
__device__ __forceinline__ uint32_t movt(uint32_t a){uint32_t d; asm volatile("movmatrix.sync.aligned.m8n8.trans.b16 %0,%1;":"=r"(d):"r"(a)); return d;}
__device__ __forceinline__ void bar_sync(int id,int n){asm volatile("bar.sync %0,%1;"::"r"(id),"r"(n):"memory");}
__device__ __forceinline__ void bar_arrive(int id,int n){asm volatile("bar.arrive %0,%1;"::"r"(id),"r"(n):"memory");}
__device__ __forceinline__ void cp16(uint32_t d,const void* s){asm volatile("cp.async.cg.shared.global [%0],[%1],16;"::"r"(d),"l"(s):"memory");}
__device__ __forceinline__ void sts32(uint32_t a,uint32_t v){asm volatile("st.shared.b32 [%0],%1;"::"r"(a),"r"(v):"memory");}
__device__ __forceinline__ uint32_t lds32(uint32_t a){uint32_t v; asm volatile("ld.shared.b32 %0,[%1];":"=r"(v):"r"(a):"memory"); return v;}
__device__ __forceinline__ void sts64(uint32_t a,float x,float y){asm volatile("st.shared.v2.f32 [%0],{%1,%2};"::"r"(a),"f"(x),"f"(y):"memory");}
__device__ __forceinline__ void sts128f(uint32_t a,const float (&v)[4]){asm volatile("st.shared.v4.f32 [%0],{%1,%2,%3,%4};"::"r"(a),"f"(v[0]),"f"(v[1]),"f"(v[2]),"f"(v[3]):"memory");}
__device__ __forceinline__ void lds128f(float (&v)[4],uint32_t a){asm volatile("ld.shared.v4.f32 {%0,%1,%2,%3},[%4];":"=f"(v[0]),"=f"(v[1]),"=f"(v[2]),"=f"(v[3]):"r"(a):"memory");}
__device__ __forceinline__ void lds128u(uint32_t (&v)[4],uint32_t a){asm volatile("ld.shared.v4.b32 {%0,%1,%2,%3},[%4];":"=r"(v[0]),"=r"(v[1]),"=r"(v[2]),"=r"(v[3]):"r"(a):"memory");}
__device__ __forceinline__ void sts128u(uint32_t a,const uint32_t (&v)[4]){asm volatile("st.shared.v4.b32 [%0],{%1,%2,%3,%4};"::"r"(a),"r"(v[0]),"r"(v[1]),"r"(v[2]),"r"(v[3]):"memory");}
__device__ __forceinline__ float lds32f(uint32_t a){float v; asm volatile("ld.shared.f32 %0,[%1];":"=f"(v):"r"(a):"memory"); return v;}
__device__ __forceinline__ float bf16r(float x){return __bfloat162float(__float2bfloat16_rn(x));}
__device__ __forceinline__ void bf16r2(float &a,float &b);
__device__ __forceinline__ float bflo(uint32_t w){return __uint_as_float(w<<16);}
__device__ __forceinline__ float bfhi(uint32_t w){return __uint_as_float(w&0xffff0000u);}
__device__ __forceinline__ void bf16r2(float &a,float &b){ const uint32_t w=pack2(a,b); a=bflo(w); b=bfhi(w); }
__device__ __forceinline__ uint2 ldg_rlx2(const void* p){uint2 v; asm volatile("ld.relaxed.gpu.global.v2.b32 {%0,%1},[%2];":"=r"(v.x),"=r"(v.y):"l"(p):"memory"); return v;}
__device__ __forceinline__ uint32_t ldg_rlx1(const void* p){uint32_t v; asm volatile("ld.relaxed.gpu.global.b32 %0,[%1];":"=r"(v):"l"(p):"memory"); return v;}
__device__ __forceinline__ void stg_rlx(void* p,uint32_t v){asm volatile("st.relaxed.gpu.global.b32 [%0],%1;"::"l"(p),"r"(v):"memory");}
__device__ __forceinline__ unsigned ld_acq(const unsigned* p){unsigned v; asm volatile("ld.acquire.gpu.global.b32 %0,[%1];":"=r"(v):"l"(p):"memory"); return v;}
__device__ __forceinline__ void red_rel(unsigned* p,unsigned v){asm volatile("red.release.gpu.global.add.u32 [%0],%1;"::"l"(p),"r"(v):"memory");}
__device__ __forceinline__ void wait_ge(const unsigned* p,unsigned target){
  int n=0; while((int)(ld_acq(p)-target)<0){ if(++n>(1<<24)) asm volatile("trap;"); __nanosleep(20); }
}
__device__ __forceinline__ unsigned clk32(){unsigned t; asm volatile("mov.u32 %0,%%clock;":"=r"(t)); return t;}
__device__ __forceinline__ void bulk_g2s(uint32_t dst,const void* src,uint32_t bytes,uint32_t bar){
  asm volatile("cp.async.bulk.shared::cluster.global.mbarrier::complete_tx::bytes [%0],[%1],%2,[%3];"::"r"(dst),"l"(src),"r"(bytes),"r"(bar):"memory");}
__device__ __forceinline__ void tma2d(uint32_t dst,const void* map,int c0,int c1,uint32_t bar){
  asm volatile("cp.async.bulk.tensor.2d.shared::cluster.global.mbarrier::complete_tx::bytes [%0],[%1,{%3,%4}],[%2];"::"r"(dst),"l"(map),"r"(bar),"r"(c0),"r"(c1):"memory");}
__device__ __forceinline__ void fence_async(){asm volatile("fence.proxy.async;":::"memory");}
constexpr int G_STAGES=4;
constexpr int G_STAGE_BYTES=49152;
constexpr int GS_BAR=0;
constexpr int GS_ITEM=256;
constexpr int GS_RED=512;
constexpr int GS_STAGE=10240;
constexpr int GS_TOTAL=GS_STAGE+G_STAGES*G_STAGE_BYTES;
constexpr int GB_FULL=0,GB_EMPTY=4,GB_IFULL=8,GB_INEXT=10,GB_KVX=11,GB_KVM=12,GB_SFULL=16,GB_SEMPTY=18;
constexpr int GS_SIG=320;
constexpr int N_T1=43,N_T2=32;
constexpr int N_Q1=512;
#define QA_LEAD 1
constexpr int Q2_BLK=40;
constexpr int Q2_END=16*Q2_BLK;
constexpr int N_Q2=Q2_END+32+16+16;

constexpr int C_MOD=0,C_H=1,C_KV=17,C_O=33,C_OP=49,C_FIN=65,C_ACT=66,C_MOD2=67,C_DONE=68,C_Q=69  ,C_O15=73,C_NUM=89;
__device__ unsigned g_cnt[C_NUM*32];
__device__ unsigned g_prog[64*32];
__device__ unsigned g_epoch;
__device__ __align__(16) bf16 g_mod[3072];
__device__ __align__(16) uint32_t g_modt[1024];
__device__ __align__(1024) bf16 g_h[2048*512];
__device__ __align__(1024) bf16 g_kvx[64*32*2*4096];
__device__ __align__(1024) bf16 g_kvm[64*32*2*1024];
__device__ __align__(1024) bf16 g_o[2048*4096];
__device__ __align__(1024) float g_part[16*4*128*512];
__device__ __align__(1024) float g_part15[16*128*512];
__device__ __align__(1024) bf16 g_x1[2048*512];
__device__ __align__(1024) bf16 g_h2[2048*512];
__device__ float g_r[2048];
__device__ float g_act[2*1376];
__device__ float g_tdummy;
__device__ int g_sel[2];
__device__ __align__(1024) uint32_t g_rpart[2*8*8*256];

__device__ __forceinline__ void launch_done(unsigned E,unsigned total){
  __threadfence(); const unsigned v=atomicAdd(&g_cnt[C_DONE*32],1u);
  if(v-E*total==total-1){ g_cnt[(C_Q+((E+1)&1)*2)*32]=0; g_cnt[(C_Q+((E+1)&1)*2+1)*32]=0; __threadfence(); *(volatile unsigned*)&g_epoch=E+1; }
}
struct GP {
  CUtensorMap mq,mk,mv,mo;
  const bf16 *x,*c,*wmod,*wr,*wgate,*wup,*wdown;
  bf16* out;
};

__device__ __forceinline__ uint64_t desc_kmaj(uint32_t a){
  return (uint64_t)((a&0x3FFFF)>>4) | ((uint64_t)(128>>4)<<16) | ((uint64_t)(1024>>4)<<32); }
__device__ __forceinline__ uint64_t desc_nmaj128(uint32_t a){
  return (uint64_t)((a&0x3FFFF)>>4) | ((uint64_t)(8192>>4)<<16) | ((uint64_t)(1024>>4)<<32) | (1ull<<62); }

__device__ __forceinline__ void wgmma256(float (&d)[128],uint64_t da,uint64_t db,int acc){
  asm volatile("{\n.reg .pred p;\nsetp.ne.b32 p,%130,0;\n"
  "wgmma.mma_async.sync.aligned.m64n256k16.f32.bf16.bf16 "
  "{%0,%1,%2,%3,%4,%5,%6,%7,%8,%9,%10,%11,%12,%13,%14,%15,%16,%17,%18,%19,%20,%21,%22,%23,%24,%25,%26,%27,%28,%29,%30,%31,"
  "%32,%33,%34,%35,%36,%37,%38,%39,%40,%41,%42,%43,%44,%45,%46,%47,%48,%49,%50,%51,%52,%53,%54,%55,%56,%57,%58,%59,%60,%61,%62,%63,"
  "%64,%65,%66,%67,%68,%69,%70,%71,%72,%73,%74,%75,%76,%77,%78,%79,%80,%81,%82,%83,%84,%85,%86,%87,%88,%89,%90,%91,%92,%93,%94,%95,"
  "%96,%97,%98,%99,%100,%101,%102,%103,%104,%105,%106,%107,%108,%109,%110,%111,%112,%113,%114,%115,%116,%117,%118,%119,%120,%121,%122,%123,%124,%125,%126,%127},"
  "%128,%129,p,1,1,0,1;\n}"
  :"+f"(d[0]),"+f"(d[1]),"+f"(d[2]),"+f"(d[3]),"+f"(d[4]),"+f"(d[5]),"+f"(d[6]),"+f"(d[7]),"+f"(d[8]),"+f"(d[9]),"+f"(d[10]),"+f"(d[11]),"+f"(d[12]),"+f"(d[13]),"+f"(d[14]),"+f"(d[15]),
   "+f"(d[16]),"+f"(d[17]),"+f"(d[18]),"+f"(d[19]),"+f"(d[20]),"+f"(d[21]),"+f"(d[22]),"+f"(d[23]),"+f"(d[24]),"+f"(d[25]),"+f"(d[26]),"+f"(d[27]),"+f"(d[28]),"+f"(d[29]),"+f"(d[30]),"+f"(d[31]),
   "+f"(d[32]),"+f"(d[33]),"+f"(d[34]),"+f"(d[35]),"+f"(d[36]),"+f"(d[37]),"+f"(d[38]),"+f"(d[39]),"+f"(d[40]),"+f"(d[41]),"+f"(d[42]),"+f"(d[43]),"+f"(d[44]),"+f"(d[45]),"+f"(d[46]),"+f"(d[47]),
   "+f"(d[48]),"+f"(d[49]),"+f"(d[50]),"+f"(d[51]),"+f"(d[52]),"+f"(d[53]),"+f"(d[54]),"+f"(d[55]),"+f"(d[56]),"+f"(d[57]),"+f"(d[58]),"+f"(d[59]),"+f"(d[60]),"+f"(d[61]),"+f"(d[62]),"+f"(d[63]),
   "+f"(d[64]),"+f"(d[65]),"+f"(d[66]),"+f"(d[67]),"+f"(d[68]),"+f"(d[69]),"+f"(d[70]),"+f"(d[71]),"+f"(d[72]),"+f"(d[73]),"+f"(d[74]),"+f"(d[75]),"+f"(d[76]),"+f"(d[77]),"+f"(d[78]),"+f"(d[79]),
   "+f"(d[80]),"+f"(d[81]),"+f"(d[82]),"+f"(d[83]),"+f"(d[84]),"+f"(d[85]),"+f"(d[86]),"+f"(d[87]),"+f"(d[88]),"+f"(d[89]),"+f"(d[90]),"+f"(d[91]),"+f"(d[92]),"+f"(d[93]),"+f"(d[94]),"+f"(d[95]),
   "+f"(d[96]),"+f"(d[97]),"+f"(d[98]),"+f"(d[99]),"+f"(d[100]),"+f"(d[101]),"+f"(d[102]),"+f"(d[103]),"+f"(d[104]),"+f"(d[105]),"+f"(d[106]),"+f"(d[107]),"+f"(d[108]),"+f"(d[109]),"+f"(d[110]),"+f"(d[111]),
   "+f"(d[112]),"+f"(d[113]),"+f"(d[114]),"+f"(d[115]),"+f"(d[116]),"+f"(d[117]),"+f"(d[118]),"+f"(d[119]),"+f"(d[120]),"+f"(d[121]),"+f"(d[122]),"+f"(d[123]),"+f"(d[124]),"+f"(d[125]),"+f"(d[126]),"+f"(d[127])
  :"l"(da),"l"(db),"r"(acc));
}

__device__ __forceinline__ void ln16(float (&v)[16]){
  float s=0.f;
  #pragma unroll
  for(int i=0;i<16;i++) s+=v[i];
  #pragma unroll
  for(int o=16;o;o>>=1) s+=__shfl_xor_sync(0xffffffffu,s,o);
  const float mf=s*(1.f/512.f);
  float q=0.f;
  #pragma unroll
  for(int i=0;i<16;i++){ float d=v[i]-mf; q+=d*d; }
  #pragma unroll
  for(int o=16;o;o>>=1) q+=__shfl_xor_sync(0xffffffffu,q,o);
  float m=mf, var=q*(1.f/512.f); bf16r2(m,var);
  const float sd=bf16r(sqrtf(bf16r(var+1e-5f)));
  const float inv=__frcp_rn(sd);
  #pragma unroll
  for(int i=0;i<16;i+=2){ float a=v[i]-m,b=v[i+1]-m; bf16r2(a,b); a*=inv; b*=inv; bf16r2(a,b); v[i]=a; v[i+1]=b; }
}
__device__ __forceinline__ void mod16(float (&v)[16],const float (&sc)[16],const float (&sh)[16]){
  #pragma unroll
  for(int i=0;i<16;i+=2){ float a=v[i]*sc[i],b=v[i+1]*sc[i+1]; bf16r2(a,b); a+=sh[i]; b+=sh[i+1]; bf16r2(a,b); v[i]=a; v[i+1]=b; }
}
__device__ __forceinline__ void ld_row16(float (&v)[16],const bf16* row,int lane){
  uint4 a=*(const uint4*)(row+8*lane), b=*(const uint4*)(row+256+8*lane);
  v[0]=bflo(a.x);v[1]=bfhi(a.x);v[2]=bflo(a.y);v[3]=bfhi(a.y);v[4]=bflo(a.z);v[5]=bfhi(a.z);v[6]=bflo(a.w);v[7]=bfhi(a.w);
  v[8]=bflo(b.x);v[9]=bfhi(b.x);v[10]=bflo(b.y);v[11]=bfhi(b.y);v[12]=bflo(b.z);v[13]=bfhi(b.z);v[14]=bflo(b.w);v[15]=bfhi(b.w);
}
__device__ __forceinline__ void ld_pk(uint4 &a,uint4 &b,const bf16* row,int lane){ a=__ldcg((const uint4*)(row+8*lane)); b=__ldcg((const uint4*)(row+256+8*lane)); }
__device__ __forceinline__ void unpk(float (&v)[16],const uint4 &a,const uint4 &b){
  v[0]=bflo(a.x);v[1]=bfhi(a.x);v[2]=bflo(a.y);v[3]=bfhi(a.y);v[4]=bflo(a.z);v[5]=bfhi(a.z);v[6]=bflo(a.w);v[7]=bfhi(a.w);
  v[8]=bflo(b.x);v[9]=bfhi(b.x);v[10]=bflo(b.y);v[11]=bfhi(b.y);v[12]=bflo(b.z);v[13]=bfhi(b.z);v[14]=bflo(b.w);v[15]=bfhi(b.w);
}
__device__ __forceinline__ void ld_vec16(float (&v)[16],const float* p,int lane){
  #pragma unroll
  for(int hh=0;hh<2;hh++){ float4 a=__ldcg((const float4*)(p+hh*256+8*lane)), b=__ldcg((const float4*)(p+hh*256+8*lane+4));
    v[hh*8+0]=a.x;v[hh*8+1]=a.y;v[hh*8+2]=a.z;v[hh*8+3]=a.w;v[hh*8+4]=b.x;v[hh*8+5]=b.y;v[hh*8+6]=b.z;v[hh*8+7]=b.w; }
}
__device__ __forceinline__ float ex2f(float x){ float y; asm("ex2.approx.ftz.f32 %0,%1;":"=f"(y):"f"(x)); return y; }
template<int NCOL>
__device__ __forceinline__ void mod_slice(const bf16* c,const bf16* wmod,bf16* outp,int n0,float* red,int tid,int barid,uint32_t* tagged=nullptr,uint32_t tag=0){
  constexpr int CO=NCOL/8, KL=256/CO, NI=512/KL;
  const int co=tid%CO, kl=tid/CO, lane=tid&31, warp=tid>>5;
  uint4 wv[NI]; float sv[NI];
  #pragma unroll
  for(int i=0;i<NI;i++){ const int k=kl+KL*i; wv[i]=__ldg((const uint4*)(wmod+(size_t)k*3072+n0+co*8)); sv[i]=__bfloat162float(__ldg(c+k)); }
  #pragma unroll
  for(int i=0;i<NI;i++) sv[i]=bf16r(__fdividef(sv[i],1.f+__expf(-sv[i])));
  float acc[8];
  #pragma unroll
  for(int q=0;q<8;q++) acc[q]=0.f;
  #pragma unroll
  for(int i=0;i<NI;i++){
    acc[0]+=sv[i]*bflo(wv[i].x);acc[1]+=sv[i]*bfhi(wv[i].x);acc[2]+=sv[i]*bflo(wv[i].y);acc[3]+=sv[i]*bfhi(wv[i].y);
    acc[4]+=sv[i]*bflo(wv[i].z);acc[5]+=sv[i]*bfhi(wv[i].z);acc[6]+=sv[i]*bflo(wv[i].w);acc[7]+=sv[i]*bfhi(wv[i].w); }
  #pragma unroll
  for(int q=0;q<8;q++){
    #pragma unroll
    for(int o=CO;o<32;o<<=1) acc[q]+=__shfl_xor_sync(0xffffffffu,acc[q],o); }
  if(lane<CO){
    #pragma unroll
    for(int q=0;q<8;q++) red[warp*NCOL+lane*8+q]=acc[q]; }
  bar_sync(barid,256);
  if(tid<NCOL){ float s=0.f;
    #pragma unroll
    for(int q=0;q<8;q++) s+=red[q*NCOL+tid];
    const bf16 v=__float2bfloat16_rn(s); outp[n0+tid]=v;
    if(tagged) stg_rlx(tagged+n0+tid,((uint32_t)__bfloat16_as_ushort(v)<<16)|tag); }
  bar_sync(barid,256);
}
__device__ __forceinline__ uint4 pack8(const float* v){ return make_uint4(pack2(v[0],v[1]),pack2(v[2],v[3]),pack2(v[4],v[5]),pack2(v[6],v[7])); }

__device__ __forceinline__ void decode_q2(int i,int &type,int &b,int &u){
  if(i<Q2_END){ const int bb=i/Q2_BLK, j=i-bb*Q2_BLK;
    if(j<16){ type=1; b=bb; u=j; }
    else if(j<24){ b=bb-1; u=j-16; type=(b>=0)?2:8; }
    else { b=bb-2; u=j-24; type=(b>=0)?3:8; } }
  else { int j=i-Q2_END;
    if(j<32){ type=7; b=15; u=j; }
    else if(j<48){ type=3; b=14; u=j-32; }
    else if(j<64){ type=3; b=15; u=j-48; }
    else { type=6; b=0; u=0; } }
}
__device__ __forceinline__ unsigned ld_rlx(const unsigned* p){unsigned v; asm volatile("ld.relaxed.gpu.global.b32 %0,[%1];":"=r"(v):"l"(p):"memory"); return v;}
__device__ __forceinline__ bool q2_ready(int type,int b,int u,unsigned E){
  if(type==1) return (int)(ld_rlx(&g_prog[(4*u)*32])-(E*64+max(4*b-QA_LEAD,1)))>=0 && (int)(ld_rlx(&g_cnt[(C_KV+b)*32])-(E*32+32))>=0;
  if(type==2) return (int)(ld_rlx(&g_cnt[(C_O+b)*32])-(E*16+16))>=0;
  if(type==7) return (int)(ld_rlx(&g_prog[0])-(E*64+62))>=0 && (int)(ld_rlx(&g_cnt[(C_O+14)*32])-(E*16+16))>=0;
  if(type==3) return (int)(ld_rlx(&g_cnt[(C_OP+b)*32])-(E*(b==15?32u:8u)+(b==15?32u:8u)))>=0 && (int)(ld_rlx(&g_cnt[C_MOD2*32])-(E*64+64))>=0;
  return true;
}

__global__ void __launch_bounds__(384,1) gkernel(const __grid_constant__ GP P){
  extern __shared__ __align__(1024) uint8_t smem[];
  const uint32_t sb=s2u(smem);
  const int tid=threadIdx.x, lane=tid&31;
  const int warp=__shfl_sync(0xffffffffu,tid>>5,0);
  const unsigned E=*(volatile unsigned*)&g_epoch;
  if(tid==0){
    for(int i=0;i<G_STAGES;i++){ mbar_init(sb+GS_BAR+8*(GB_FULL+i),1); mbar_init(sb+GS_BAR+8*(GB_EMPTY+i),8); }
    mbar_init(sb+GS_BAR+8*GB_IFULL,1); mbar_init(sb+GS_BAR+8*(GB_IFULL+1),1); mbar_init(sb+GS_BAR+8*GB_INEXT,8);
    mbar_init(sb+GS_BAR+8*GB_KVX,1); for(int i=0;i<4;i++) mbar_init(sb+GS_BAR+8*(GB_KVM+i),1);
    for(int i=0;i<2;i++){ mbar_init(sb+GS_BAR+8*(GB_SFULL+i),8); mbar_init(sb+GS_BAR+8*(GB_SEMPTY+i),1); }
    asm volatile("fence.mbarrier_init.release.cluster;":::"memory");
  }
  __syncthreads();

  if(warp>=8){
    asm volatile("setmaxnreg.dec.sync.aligned.u32 40;");
    if(warp==9 && lane==0){
      for(uint32_t k=0;;k++){
        mbar_wait(sb+GS_BAR+8*(GB_SFULL+(k&1)),(k>>1)&1);
        const uint32_t idx=lds32(sb+GS_SIG+(k&1)*4);
        if(idx==0xffffffffu) break;
        asm volatile("fence.acq_rel.gpu;":::"memory");
        asm volatile("red.relaxed.gpu.global.add.u32 [%0],1;"::"l"(&g_cnt[idx*32]):"memory");
        mbar_arrive(sb+GS_BAR+8*(GB_SEMPTY+(k&1)));
      }
    }
    if(warp==8 && lane==0){
      unsigned* q1=&g_cnt[(C_Q+(E&1)*2)*32]; unsigned* q2=&g_cnt[(C_Q+(E&1)*2+1)*32];
      uint32_t it=0;
      bool wpre=false;
      for(uint32_t k=0;;k++){
        if(k>0) mbar_wait(sb+GS_BAR+8*GB_INEXT,(k-1)&1);
        int type,b,u;
        for(int spin=0;;spin++){
          const int p2=(int)ld_rlx(q2), p1=(int)ld_rlx(q1);
          int t2=6,b2=0,u2=0; if(p2<N_Q2) decode_q2(p2,t2,b2,u2);
          const bool r2=(p2<N_Q2)&&q2_ready(t2,b2,u2,E);
          if(r2){ const int i=(int)atomicAdd(q2,1u); if(i<N_Q2){ decode_q2(i,type,b,u); if(type==8) continue; break; } else continue; }
          if(p1<N_Q1){ const int i=(int)atomicAdd(q1,1u); if(i<N_Q1){ type=0; b=i>>5; u=i&31; break; } else continue; }
          if(p2>=N_Q2){ type=6; b=0; u=0; break; }
          if(spin>(1<<22)) asm volatile("trap;");
          __nanosleep(100);
        }
        if(type==3){ for(int spin=0;!q2_ready(3,b,u,E);spin++){ if(spin>(1<<24)) asm volatile("trap;"); } asm volatile("fence.acq_rel.gpu;":::"memory"); }
        sts32(sb+GS_ITEM+(k&1)*4,(uint32_t)(type|(b<<8)|(u<<16)));
        mbar_arrive(sb+GS_BAR+8*(GB_IFULL+(k&1)));
        if(type==6) break;
        if(type>2&&type!=7) continue;
        int nk; const bf16* A; const CUtensorMap* mp; int n0,k0; const unsigned* dep; unsigned tgt;
        if(type==0){ nk=8; A=g_h+(size_t)b*8*8192; mp=(u<16)?&P.mk:&P.mv; n0=(u&15)*256; k0=0; dep=&g_cnt[(C_H+b)*32]; tgt=E*16+16; }
        else if(type==1){ nk=8; A=g_h+(size_t)b*8*8192; mp=&P.mq; n0=u*256; k0=0; dep=&g_cnt[(C_H+b)*32]; tgt=E*16+16; }
        else if(type==2){ nk=16; int kq=u>>1; A=g_o+((size_t)b*64+kq*16)*8192; mp=&P.mo; n0=(u&1)*256; k0=kq*1024; dep=&g_cnt[(C_O+b)*32]; tgt=E*16+16; }
        else { nk=4; int kq=u>>1; A=g_o+((size_t)15*64+kq*4)*8192; mp=&P.mo; n0=(u&1)*256; k0=kq*256; dep=&g_cnt[(C_O15+kq)*32]; tgt=E+1; }
        for(int kc=0;kc<4;kc++){
          const uint32_t st=(it+kc)&3;
          mbar_wait(sb+GS_BAR+8*(GB_EMPTY+st),(((it+kc)>>2)&1)^1);
          const uint32_t fb=sb+GS_BAR+8*(GB_FULL+st), dst=sb+GS_STAGE+st*G_STAGE_BYTES;
          mbar_expect(fb,G_STAGE_BYTES);
          #pragma unroll
          for(int q=0;q<4;q++) tma2d(dst+16384+q*8192,mp,n0+q*64,k0+kc*64,fb);
        }
        wait_ge(dep,tgt);
        fence_async();
        for(int kc=0;kc<4;kc++){ const uint32_t st=(it+kc)&3; bulk_g2s(sb+GS_STAGE+st*G_STAGE_BYTES,A+(size_t)kc*8192,16384,sb+GS_BAR+8*(GB_FULL+st)); }
        it+=4;
        for(int kc=4;kc<nk;kc++,it++){
          const uint32_t st=it&3;
          mbar_wait(sb+GS_BAR+8*(GB_EMPTY+st),((it>>2)&1)^1);
          const uint32_t fb=sb+GS_BAR+8*(GB_FULL+st), dst=sb+GS_STAGE+st*G_STAGE_BYTES;
          mbar_expect(fb,G_STAGE_BYTES);
          bulk_g2s(dst,A+(size_t)kc*8192,16384,fb);
          #pragma unroll
          for(int q=0;q<4;q++) tma2d(dst+16384+q*8192,mp,n0+q*64,k0+kc*64,fb);
        }
        if(type==1){
          wait_ge(&g_cnt[(C_KV+b)*32],E*32+32);
          for(int q=0;q<4;q++,it++){ const uint32_t st=it&3; mbar_wait(sb+GS_BAR+8*(GB_EMPTY+st),((it>>2)&1)^1); mbar_arrive(sb+GS_BAR+8*(GB_FULL+st)); }
          fence_async();
          const uint32_t xb=sb+GS_BAR+8*GB_KVX;
          mbar_expect(xb,131072);
          for(int hh=0;hh<2;hh++) for(int sg=0;sg<4;sg++)
            bulk_g2s(sb+GS_STAGE+(hh*4+sg)*16384,g_kvx+((size_t)(4*b+sg)*32+2*u+hh)*8192,16384,xb);
          int ok=0;
          for(int sg=0;sg<4;sg++){
            const bool polled=(ok<=sg);
            for(int spin=0;ok<=sg;spin++){
              const unsigned p0=ld_rlx(&g_prog[(4*u)*32]),p1=ld_rlx(&g_prog[(4*u+1)*32]),p2=ld_rlx(&g_prog[(4*u+2)*32]),p3=ld_rlx(&g_prog[(4*u+3)*32]);
              const unsigned base=E*64+4*b;
              int mn=min(min((int)(p0-base),(int)(p1-base)),min((int)(p2-base),(int)(p3-base)));
              ok=max(0,min(mn,4));
              if(spin>(1<<24)) asm volatile("trap;");
            }
            if(polled){ asm volatile("fence.acq_rel.gpu;":::"memory"); fence_async(); }
            const uint32_t mb=sb+GS_BAR+8*(GB_KVM+sg);
            mbar_expect(mb,8192);
            for(int hh=0;hh<2;hh++) bulk_g2s(sb+GS_STAGE+131072+(hh*4+sg)*4096,g_kvm+((size_t)(4*b+sg)*32+2*u+hh)*2048,4096,mb);
          }
          mbar_wait(sb+GS_BAR+8*(GB_EMPTY+((it-1)&3)),(((it+3)>>2)&1)^1);
        }
      }
      (void)wpre;
    }
  } else {
    asm volatile("setmaxnreg.inc.sync.aligned.u32 232;");
    const int wg=warp>>2, w=warp&3;
    uint32_t it=0, nq=0, ns=0;
    float d[128];
    auto signal=[&](uint32_t idx){
      const uint32_t sl=ns&1;
      mbar_wait(sb+GS_BAR+8*(GB_SEMPTY+sl),((ns>>1)&1)^1);
      if(tid==0) sts32(sb+GS_SIG+sl*4,idx);
      bar_sync(1,256);
      if(lane==0) mbar_arrive(sb+GS_BAR+8*(GB_SFULL+sl));
      ns++;
    };
    for(uint32_t k=0;;k++){
      mbar_wait(sb+GS_BAR+8*(GB_IFULL+(k&1)),(k>>1)&1);
      const uint32_t iw=lds32(sb+GS_ITEM+(k&1)*4);
      const int type=iw&0xff, b=(iw>>8)&0xff, u=iw>>16;
      __syncwarp();
      if(lane==0) mbar_arrive(sb+GS_BAR+8*GB_INEXT);
      if(type==6) break;
      if(type<=2||type==7){
        const int nk=(type==2)?16:(type==7)?4:8;
        #pragma unroll
        for(int i=0;i<128;i++) d[i]=0.f;
        for(int kc=0;kc<nk;kc++,it++){
          const uint32_t st=it&3;
          mbar_wait(sb+GS_BAR+8*(GB_FULL+st),(it>>2)&1);
          const uint32_t a0=sb+GS_STAGE+st*G_STAGE_BYTES+wg*8192, b0=sb+GS_STAGE+st*G_STAGE_BYTES+16384;
          asm volatile("wgmma.fence.sync.aligned;":::"memory");
          #pragma unroll
          for(int ks=0;ks<4;ks++) wgmma256(d,desc_kmaj(a0+ks*256),desc_nmaj128(b0+ks*2048),1);
          asm volatile("wgmma.commit_group.sync.aligned;":::"memory");
          if(kc>0){ asm volatile("wgmma.wait_group.sync.aligned 1;":::"memory");
            if(lane==0) mbar_arrive(sb+GS_BAR+8*(GB_EMPTY+((it-1)&3))); }
        }
        asm volatile("wgmma.wait_group.sync.aligned 0;":::"memory");
        if(lane==0) mbar_arrive(sb+GS_BAR+8*(GB_EMPTY+((it-1)&3)));
      }
      if(type==0){
        const int seg=4*b+2*wg+(w>>1), isv=u>>4, h0=(u&15)*2;
        bf16* base=g_kvx+((size_t)seg*32+h0)*8192+isv*2048+(2*(w&1))*512+lane*2;
        #pragma unroll
        for(int j=0;j<32;j++){
          bf16* p=base+(size_t)(j>>4)*8192+((j>>3)&1)*4096+(j&7)*64;
          *(uint32_t*)p=pack2(d[4*j],d[4*j+1]);
          *(uint32_t*)(p+512)=pack2(d[4*j+2],d[4*j+3]);
        }
        signal(C_KV+b);
      } else if(type==1){
        uint32_t qa[2][8][4];
        #pragma unroll
        for(int hh=0;hh<2;hh++)
          #pragma unroll
          for(int ks=0;ks<8;ks++){ const int j=16*hh+2*ks;
            qa[hh][ks][0]=pack2(d[4*j],d[4*j+1]); qa[hh][ks][1]=pack2(d[4*j+2],d[4*j+3]);
            qa[hh][ks][2]=pack2(d[4*j+4],d[4*j+5]); qa[hh][ks][3]=pack2(d[4*j+6],d[4*j+7]); }
        const int sg=2*wg+(w>>1), up=w&1;
        mbar_wait(sb+GS_BAR+8*GB_KVX,nq&1);
        mbar_wait(sb+GS_BAR+8*(GB_KVM+sg),nq&1);
        #pragma unroll 1
        for(int hh=0;hh<2;hh++){
          const uint32_t xb=sb+GS_STAGE+(hh*4+sg)*16384;
          const uint32_t mb=sb+GS_STAGE+131072+(hh*4+sg)*4096;
          float s[5][4];
          #pragma unroll
          for(int nt=0;nt<5;nt++){
            s[nt][0]=s[nt][1]=s[nt][2]=s[nt][3]=0.f;
            if(nt<3||up){
              #pragma unroll
              for(int kp=0;kp<4;kp++){
                const uint32_t blk=(nt==0)? (mb+(kp>>1)*2048) : (xb+(kp>>1)*8192+(nt-1)*1024);
                uint32_t bb[4]; ldsm4(bb,blk+(kp&1)*512+lane*16);
                mma16816(s[nt],qa[0][2*kp],bb[0],bb[1]); mma16816(s[nt],qa[0][2*kp+1],bb[2],bb[3]);
              }
            }
          }
          const float scale=0.08838834764831845f;
          const int q0=16*up+(lane>>2), q1=q0+8;
          float m0=-INFINITY,m1=-INFINITY;
          #pragma unroll
          for(int nt=0;nt<5;nt++){
            bf16r2(s[nt][0],s[nt][1]); bf16r2(s[nt][2],s[nt][3]);
            #pragma unroll
            for(int e=0;e<4;e++) s[nt][e]*=scale;
            bf16r2(s[nt][0],s[nt][1]); bf16r2(s[nt][2],s[nt][3]);
            if(nt>0){
              #pragma unroll
              for(int e=0;e<4;e++){ const int key=(nt-1)*8+2*(lane&3)+(e&1); if(key>((e&2)?q1:q0)) s[nt][e]=-INFINITY; }
            }
            m0=fmaxf(m0,fmaxf(s[nt][0],s[nt][1])); m1=fmaxf(m1,fmaxf(s[nt][2],s[nt][3]));
          }
          m0=fmaxf(m0,__shfl_xor_sync(0xffffffffu,m0,1)); m0=fmaxf(m0,__shfl_xor_sync(0xffffffffu,m0,2));
          m1=fmaxf(m1,__shfl_xor_sync(0xffffffffu,m1,1)); m1=fmaxf(m1,__shfl_xor_sync(0xffffffffu,m1,2));
          float l0=0.f,l1=0.f; const float L2E=1.4426950408889634f;
          #pragma unroll
          for(int nt=0;nt<5;nt++){
            s[nt][0]=ex2f((s[nt][0]-m0)*L2E); s[nt][1]=ex2f((s[nt][1]-m0)*L2E);
            s[nt][2]=ex2f((s[nt][2]-m1)*L2E); s[nt][3]=ex2f((s[nt][3]-m1)*L2E);
            l0+=s[nt][0]+s[nt][1]; l1+=s[nt][2]+s[nt][3];
          }
          l0+=__shfl_xor_sync(0xffffffffu,l0,1); l0+=__shfl_xor_sync(0xffffffffu,l0,2);
          l1+=__shfl_xor_sync(0xffffffffu,l1,1); l1+=__shfl_xor_sync(0xffffffffu,l1,2);
          const float i0=__frcp_rn(l0), i1=__frcp_rn(l1);
          uint32_t pa[3][4];
          pa[0][0]=pack2(s[0][0]*i0,s[0][1]*i0); pa[0][1]=pack2(s[0][2]*i1,s[0][3]*i1);
          pa[0][2]=pack2(s[1][0]*i0,s[1][1]*i0); pa[0][3]=pack2(s[1][2]*i1,s[1][3]*i1);
          pa[1][0]=pack2(s[2][0]*i0,s[2][1]*i0); pa[1][1]=pack2(s[2][2]*i1,s[2][3]*i1);
          pa[1][2]=pack2(s[3][0]*i0,s[3][1]*i0); pa[1][3]=pack2(s[3][2]*i1,s[3][3]*i1);
          pa[2][0]=pack2(s[4][0]*i0,s[4][1]*i0); pa[2][1]=pack2(s[4][2]*i1,s[4][3]*i1); pa[2][2]=0; pa[2][3]=0;
          const int m=lane>>3;
          bf16* ob=g_o+((size_t)b*64+(2*u+hh)*2)*8192+(8*wg+2*w)*512+lane*2;
          #pragma unroll 2
          for(int ep=0;ep<8;ep++){
            const int jj=ep>>2; const uint32_t eo=((ep&3)*2+(m>>1))*128+(lane&7)*16;
            float o0[4]={0,0,0,0},o1[4]={0,0,0,0};
            uint32_t vb[4];
            ldsm4t(vb,((m&1)? (xb+jj*8192+4096) : (mb+jj*2048+1024))+eo);
            mma16816(o0,pa[0],vb[0],vb[1]); mma16816(o1,pa[0],vb[2],vb[3]);
            ldsm4t(vb,xb+jj*8192+4096+(1+(m&1))*1024+eo);
            mma16816(o0,pa[1],vb[0],vb[1]); mma16816(o1,pa[1],vb[2],vb[3]);
            if(up){
              ldsm4t(vb,xb+jj*8192+4096+3*1024+eo);
              mma16816(o0,pa[2],vb[0],vb[1]); mma16816(o1,pa[2],vb[2],vb[3]);
            }
            bf16* p=ob+(size_t)jj*8192+((ep&3)*2)*64;
            *(uint32_t*)p=pack2(o0[0],o0[1]);      *(uint32_t*)(p+512)=pack2(o0[2],o0[3]);
            *(uint32_t*)(p+64)=pack2(o1[0],o1[1]); *(uint32_t*)(p+64+512)=pack2(o1[2],o1[3]);
          }
          #pragma unroll
          for(int ks=0;ks<8;ks++){ qa[0][ks][0]=qa[1][ks][0]; qa[0][ks][1]=qa[1][ks][1]; qa[0][ks][2]=qa[1][ks][2]; qa[0][ks][3]=qa[1][ks][3]; }
        }
        __syncwarp();
        if(lane==0){ for(int q=0;q<4;q++) mbar_arrive(sb+GS_BAR+8*(GB_EMPTY+((it+q)&3))); }
        it+=4; nq++;
        signal(C_O+b);
        if(b==15) signal(C_O15+u);
      } else if(type==2||type==7){
        const int kq=u>>1, nh=u&1;
        float* base=((type==2)? (g_part+((size_t)b*4+kq)*128*512) : (g_part15+(size_t)kq*128*512))+(64*wg+16*w+(lane>>2))*512+nh*256+2*(lane&3);
        #pragma unroll
        for(int j=0;j<32;j++){
          *(float2*)(base+8*j)=make_float2(d[4*j],d[4*j+1]);
          *(float2*)(base+8*512+8*j)=make_float2(d[4*j+2],d[4*j+3]);
        }
        signal(C_OP+b);
      } else if(type==3){
        const int row=8*u+warp, t=128*b+row;
        const float* pp=((b==15)? g_part15 : (g_part+(size_t)b*4*128*512))+(size_t)row*512;
        float a[16];
        uint4 xa,xb,ga,gA,sa,sB,ca,cB,ba,bB,wa,wB;
        {
          float p0[16],p1[16],p2[16],p3[16];
          ld_vec16(p0,pp,lane); ld_vec16(p1,pp+(size_t)128*512,lane); ld_vec16(p2,pp+(size_t)2*128*512,lane); ld_vec16(p3,pp+(size_t)3*128*512,lane);
          ld_pk(xa,xb,P.x+(size_t)t*512,lane); ld_pk(ga,gA,g_mod+1024,lane); ld_pk(sa,sB,g_mod+1536,lane); ld_pk(ca,cB,g_mod+2048,lane); ld_pk(ba,bB,g_mod+2560,lane); ld_pk(wa,wB,P.wr,lane);
          #pragma unroll
          for(int i=0;i<16;i++) a[i]=(p0[i]+p1[i])+(p2[i]+p3[i]);
          if(b==15){
            #pragma unroll 1
            for(int q=1;q<4;q++){
              ld_vec16(p0,pp+(size_t)(4*q+0)*128*512,lane); ld_vec16(p1,pp+(size_t)(4*q+1)*128*512,lane);
              ld_vec16(p2,pp+(size_t)(4*q+2)*128*512,lane); ld_vec16(p3,pp+(size_t)(4*q+3)*128*512,lane);
              #pragma unroll
              for(int i=0;i<16;i++) a[i]+=(p0[i]+p1[i])+(p2[i]+p3[i]);
            }
          }
        }
        float x1[16],m1[16],m2[16];
        unpk(x1,xa,xb); unpk(m1,ga,gA); unpk(m2,ca,cB);
        #pragma unroll
        for(int i=0;i<16;i+=2){ float p=a[i],q=a[i+1]; bf16r2(p,q); p*=m1[i]; q*=m1[i+1]; bf16r2(p,q); p+=x1[i]; q+=x1[i+1]; bf16r2(p,q);
          x1[i]=p; x1[i+1]=q; a[i]=p; a[i+1]=q; m2[i]+=1.f; m2[i+1]+=1.f; bf16r2(m2[i],m2[i+1]); }
        ln16(a);
        unpk(m1,sa,sB);
        mod16(a,m2,m1);
        unpk(m1,wa,wB);
        float rs=0.f;
        #pragma unroll
        for(int i=0;i<16;i++) rs+=a[i]*m1[i];
        #pragma unroll
        for(int o=16;o;o>>=1) rs+=__shfl_xor_sync(0xffffffffu,rs,o);
        if(lane==0) g_r[t]=bf16r(rs);
        *(uint4*)(g_x1+(size_t)t*512+8*lane)=pack8(x1); *(uint4*)(g_x1+(size_t)t*512+256+8*lane)=pack8(x1+8);
        *(uint4*)(g_h2+(size_t)t*512+8*lane)=pack8(a);  *(uint4*)(g_h2+(size_t)t*512+256+8*lane)=pack8(a+8);
        unpk(m1,ba,bB);
        #pragma unroll
        for(int i=0;i<16;i+=2){ float p=m1[i]*a[i],q=m1[i+1]*a[i+1]; bf16r2(p,q); a[i]=x1[i]+p; a[i+1]=x1[i+1]+q; }
        *(uint4*)(P.out+(size_t)t*512+8*lane)=pack8(a); *(uint4*)(P.out+(size_t)t*512+256+8*lane)=pack8(a+8);
        signal(C_FIN);
      }
      if(k==0){
        for(int cb=blockIdx.x;cb<64;cb+=gridDim.x){
          mod_slice<32>(P.c,P.wmod,g_mod,1024+cb*32,(float*)(smem+GS_RED),tid,1);
          signal(C_MOD2);
        }
      }
    }
    signal(0xffffffffu);
    if(tid==0) launch_done(E,gridDim.x+64);
  }
}
constexpr int NSEG=64;
#define HREG 24
#define CREG 240
constexpr int SM_BAR=0;
constexpr int SM_MEM=1024;
constexpr int SM_O=SM_MEM+8192;
constexpr int SM_KX=SM_O+8192;
constexpr int SM_KM=SM_KX+16384;
constexpr int SM_VM=SM_KM+2048;
constexpr int SM_Q=SM_VM+2048;
constexpr int SM_ZERO=SM_Q+1024;
constexpr int SM_S=SM_ZERO+1024;
constexpr int SM_P=SM_S+4096;
constexpr int SM_RQK=SM_P+1024;
constexpr int SM_RO=SM_RQK+4096;
constexpr int SM_RV=SM_RO+2048;
constexpr int SM_TS=SM_RV+2048;
constexpr int SM_WVF=SM_TS+12288;
constexpr int SM_WOF=SM_WVF+65536;
constexpr int SM_TOTAL=SM_WOF+65536;
constexpr int B_MEM=0,B_O=8,B_S=16,B_KV=17,B_W=19;
constexpr int SROW=10;

struct RP {
  const bf16* mem0; const bf16* Wq; const bf16* Wk; const bf16* Wv; const bf16* Wo;
  const bf16 *x,*c,*wmod;
  const bf16 *wgate,*wup,*wdown; bf16* out; int ng;
  CUtensorMap mq,mk,mv,mo;
  int delay, period;
};
__device__ long long g_rtime[8];
#define STR2(x) #x
#define STR(x) STR2(x)
#define TS(i)

__device__ __forceinline__ void stage_slice(uint32_t dst,const bf16* src,int ld,int t,int nt){
  for(int i=t;i<4096;i+=nt){ int k=i>>3, eg=i&7; cp16(dst+((k>>3)*8+eg)*128+(k&7)*16,src+(size_t)k*ld+8*eg); }
}

__device__ __forceinline__ void mbar_wait_nt(uint32_t b,uint32_t par){
  asm volatile("{\n.reg .pred p;\nWL:\nmbarrier.try_wait.parity.shared::cta.b64 p,[%0],%1;\n@!p bra WL;\n}"::"r"(b),"r"(par):"memory");
}
#define W_DELAY 1500
#define NB1 6
#define NA1 0
#define LDB(buf,base,i) { ldsm4(buf##0,(base)+(i)*1024); ldsm4(buf##1,(base)+(i)*1024+512); }
template<int F>
__device__ __forceinline__ void compute_path(const RP& P,uint8_t* smem_red,const uint32_t sb,const int warp,const int lane_,const uint32_t r_,const int c,const unsigned E){
  const int g=warp&3;
  constexpr int slot0=F?0:4;
  uint32_t wq[16][4], wk[16][4], bk[16][4];
  {
    const int lane=lane_; const uint32_t r=r_; const int tid=warp*32+lane;
    const int h=4*c+(r>>1), j=r&1;
    const int m=lane>>3;
    {
      const int cta=blockIdx.x;
      const uint32_t xs=sb+SM_MEM+warp*1024+lane*16;
      #pragma unroll
      for(int q=0;q<4;q++){ const bf16* row=P.x+(size_t)((cta+64*q)*8+warp)*512; cp16(xs+q*8192,row+8*lane); cp16(xs+q*8192+512,row+256+8*lane); }
      asm volatile("cp.async.commit_group;":::"memory");
      mod_slice<16>(P.c,P.wmod,g_mod,cta*16,(float*)(smem_red),tid,10,g_modt,(E+1)&0xffffu);
      asm volatile("cp.async.wait_group 0;":::"memory");
      #pragma unroll 1
      for(int q=0;q<4;q++){
        uint32_t a[4],b[4]; lds128u(a,xs+q*8192); lds128u(b,xs+q*8192+512);
        float v[16]; unpk(v,make_uint4(a[0],a[1],a[2],a[3]),make_uint4(b[0],b[1],b[2],b[3]));
        ln16(v);
        const uint4 pa=pack8(v), pb=pack8(v+8);
        a[0]=pa.x;a[1]=pa.y;a[2]=pa.z;a[3]=pa.w; b[0]=pb.x;b[1]=pb.y;b[2]=pb.z;b[3]=pb.w;
        sts128u(xs+q*8192,a); sts128u(xs+q*8192+512,b);
      }
      float sa[16],ca1[16];
      {
        const uint32_t tag=(E+1)&0xffffu; uint4 w[8]; int n=0;
        while(true){
          bool ok=true;
          #pragma unroll
          for(int q=0;q<8;q++){ const uint32_t* p=g_modt+(q>>2)*512+((q>>1)&1)*256+8*lane+(q&1)*4;
            asm volatile("ld.relaxed.gpu.global.v4.b32 {%0,%1,%2,%3},[%4];":"=r"(w[q].x),"=r"(w[q].y),"=r"(w[q].z),"=r"(w[q].w):"l"(p):"memory"); }
          #pragma unroll
          for(int q=0;q<8;q++) ok=ok&&((((w[q].x^tag)|(w[q].y^tag)|(w[q].z^tag)|(w[q].w^tag))&0xffffu)==0);
          if(__all_sync(0xffffffffu,ok)) break;
          if(++n>(1<<22)) asm volatile("trap;");
        }
        #pragma unroll
        for(int q=0;q<4;q++){ sa[4*q]=bfhi(w[q].x);sa[4*q+1]=bfhi(w[q].y);sa[4*q+2]=bfhi(w[q].z);sa[4*q+3]=bfhi(w[q].w);
          ca1[4*q]=bfhi(w[4+q].x);ca1[4*q+1]=bfhi(w[4+q].y);ca1[4*q+2]=bfhi(w[4+q].z);ca1[4*q+3]=bfhi(w[4+q].w); }
      }
      #pragma unroll
      for(int i=0;i<16;i+=2){ ca1[i]+=1.f; ca1[i+1]+=1.f; bf16r2(ca1[i],ca1[i+1]); }
      #pragma unroll 1
      for(int q=0;q<4;q++){
        uint32_t a[4],b[4]; lds128u(a,xs+q*8192); lds128u(b,xs+q*8192+512);
        float v[16]; unpk(v,make_uint4(a[0],a[1],a[2],a[3]),make_uint4(b[0],b[1],b[2],b[3]));
        mod16(v,ca1,sa);
        const int ch=cta+64*q, bb=ch>>4, rg=ch&15;
        bf16* dst=g_h+((size_t)bb*8+(lane>>3))*8192+rg*512+(lane&7)*64+warp*8;
        *(uint4*)dst=pack8(v); *(uint4*)(dst+4*8192)=pack8(v+8);
      }
      bar_sync(10,256);
      if(tid<4) red_rel(&g_cnt[(C_H+((cta+64*tid)>>4))*32],1u);
      bar_arrive(15,288);
    }
    #define WOFF(i,ks) ((((r-(slot0+(i)))&7)*64+(ks)*16+(m>>1)*8+(lane&7))*128+(((2*g+(m&1))^(lane&7))*16))
    mbar_wait(sb+SM_BAR+8*B_W,0);
    #pragma unroll
    for(int i=0;i<4;i++){
      #pragma unroll
      for(int ks=0;ks<4;ks++){ ldsm4t(wq[i*4+ks],sb+SM_WVF+WOFF(i,ks)); ldsm4t(wk[i*4+ks],sb+SM_WOF+WOFF(i,ks)); }
    }
    bar_sync(13,288);
    mbar_wait(sb+SM_BAR+8*B_W,1);
    #pragma unroll
    for(int pass=0;pass<2;pass++){
      const uint32_t reg=sb+(pass?SM_WVF:SM_WOF);
      #pragma unroll
      for(int i=0;i<4;i++){
        #pragma unroll
        for(int ks=0;ks<4;ks++) ldsm4t(bk[i*4+ks],reg+WOFF(i,ks));
      }
      bar_sync(10,256);
      #pragma unroll
      for(int u=0;u<16;u++) sts128u(reg+(warp*16+u)*512+lane*16,bk[u]);
      bar_sync(10,256);
    }
  }
  asm volatile("barrier.cluster.arrive.release.aligned;\nbarrier.cluster.wait.acquire.aligned;":::"memory");
  const uint32_t wtags=((32u*E+1)&1)|(((31u*E+1)&1)<<1);
  unsigned t0=0;
  #pragma unroll 1
  for(int s=0;s<NSEG;s++){
    const uint32_t par=s&1;
    const bool last=(s==NSEG-1);
    int lane=lane_; asm volatile("":"+r"(lane));
    uint32_t r=r_; asm volatile("":"+r"(r));
    const int tid=warp*32+lane;
    const uint32_t l16=sb+lane*16, l4=sb+lane*4;
    const uint32_t wvf=l16+SM_WVF+warp*8192, wof=l16+SM_WOF+warp*8192;
    TS(0);
    {
      uint32_t mw;
      if(s==0){
        mw=*(const uint32_t*)(P.mem0+((tid>>2)&7)*512+64*r+(tid>>5)*8+(tid&3)*2);
      } else {
        const int ps=s-1; const uint32_t slot=ps&1;
        const uint32_t tag=((wtags>>slot)+(ps>>1))&1;
        const uint32_t* pp=g_rpart+(slot*8+r)*8*256+tid;
        uint32_t v[8];
        #pragma unroll
        for(int u=0;u<NA1;u++) lds128u(bk[u],wvf+u*512);
        while(clk32()-t0<(unsigned)P.delay);
        #pragma unroll
        for(int q=0;q<8;q++) v[q]=ldg_rlx1(pp+q*256);
        #pragma unroll
        for(int u=NA1;u<16;u++) lds128u(bk[u],wvf+u*512);
        while(true){
          bool ok=true;
          #pragma unroll
          for(int q=0;q<8;q++) if((v[q]^tag)&1){ ok=false; v[q]=ldg_rlx1(pp+q*256); }
          if(ok) break;
        }
        #define LO(x) __uint_as_float(((x)&0xfffeu)<<16)
        #define HI(x) __uint_as_float((x)&0xffff0000u)
        const float a0=((LO(v[0])+LO(v[1]))+(LO(v[2])+LO(v[3])))+((LO(v[4])+LO(v[5]))+(LO(v[6])+LO(v[7])));
        const float a1=((HI(v[0])+HI(v[1]))+(HI(v[2])+HI(v[3])))+((HI(v[4])+HI(v[5]))+(HI(v[6])+HI(v[7])));
        mw=pack2(a0,a1);
      }
      TS(1);
      bar_sync(11,256);
      #pragma unroll
      for(int i=0;i<8;i++){
        const uint32_t d=(r+i)&7;
        st_async4(mapa(sb+SM_MEM+i*1024+tid*4,d),mw,mapa(sb+SM_BAR+8*(B_MEM+i),d));
      }
    }
    TS(2);
    float av[4];
    {
      float aq[4], ak[4];
      #pragma unroll
      for(int q=0;q<4;q++){aq[q]=ak[q]=av[q]=0.f;}
      uint32_t x0[4],x1[4],y0[4],y1[4];
      const uint32_t mb=l16+SM_MEM+slot0*1024, bb=sb+SM_BAR+8*(B_MEM+slot0);
      #define QKV1(u,b,lo) { mma16816(aq,wq[u],b[lo],b[lo+1]); mma16816(ak,wk[u],b[lo],b[lo+1]); mma16816(av,bk[u],b[lo],b[lo+1]); }
      #define QKV(i,b) { QKV1(i*4+0,b##0,0) QKV1(i*4+1,b##0,2) QKV1(i*4+2,b##1,0) QKV1(i*4+3,b##1,2) }
      mbar_wait_nt(bb,par);    LDB(x,mb,0)
      mbar_wait_nt(bb+8,par);  LDB(y,mb,1)  QKV(0,x)
      mbar_wait_nt(bb+16,par); LDB(x,mb,2)  QKV(1,y)
      mbar_wait_nt(bb+24,par); LDB(y,mb,3)  QKV(2,x)
      QKV(3,y)
      const uint32_t rq=l16+SM_RQK+g*1024;
      if(F){
        TS(3);
        sts128f(rq,aq); sts128f(rq+512,ak);
        bar_arrive(1,256);
        sts128f(l16+SM_RV+g*512,av);
      } else {
        bar_sync(1,256);
        float pq[4],pk[4]; lds128f(pq,rq); lds128f(pk,rq+512);
        #pragma unroll
        for(int q=0;q<4;q++){aq[q]+=pq[q]; ak[q]+=pk[q];}
        TS(3);
        const int m=lane>>3;
        const uint32_t dst=sb+((m&2)? (SM_KM+par*1024):SM_Q)+(2*g+(m&1))*128+(lane&7)*16;
        stsm4t(dst,pack2(aq[0],aq[1]),pack2(aq[2],aq[3]),pack2(ak[0],ak[1]),pack2(ak[2],ak[3]));
        if(!last) bar_arrive(2,224);
      }
    }
    TS(4);
    if(F && g<3 && !last){
      mbar_wait_nt(sb+SM_BAR+8*(B_KV+par),(s>>1)&1);
      const int m=lane>>3;
      const int kg=2*g+(m&1);
      uint32_t abase=(kg==0)? (sb+SM_KM+par*1024) : (kg==5)? (sb+SM_ZERO) : (sb+SM_KX+par*8192+(kg-1)*1024);
      abase+=(m>>1)*128+(lane&7)*16;
      uint32_t ka[4][4];
      if(g>0){
        #pragma unroll
        for(int ks=0;ks<4;ks++) ldsm4(ka[ks],abase+ks*256);
      }
      bar_sync(2,224);
      uint32_t b0[4],b1[4];
      ldsm4(b0,l16+SM_Q);
      if(g==0){ ldsm4(ka[0],abase); ldsm4(ka[1],abase+256); }
      ldsm4(b1,l16+SM_Q+512);
      if(g==0){ ldsm4(ka[2],abase+512); ldsm4(ka[3],abase+768); }
      float sa[4]={0,0,0,0}, sc[4]={0,0,0,0};
      mma16816(sa,ka[0],b0[0],b0[1]); mma16816(sc,ka[1],b0[2],b0[3]);
      mma16816(sa,ka[2],b1[0],b1[1]); mma16816(sc,ka[3],b1[2],b1[3]);
      #pragma unroll
      for(int q=0;q<4;q++) sa[q]+=sc[q];
      const uint32_t so=sb+SM_S+((16*g+(lane>>2))*SROW+2*(lane&3))*4;
      const uint32_t pr=r^1;
      const uint32_t rs=mapa(so+2048,pr), rb=mapa(sb+SM_BAR+8*B_S,pr);
      st_async8(rs,__float_as_uint(sa[0]),__float_as_uint(sa[1]),rb);
      if(g<2) st_async8(rs+8*SROW*4,__float_as_uint(sa[2]),__float_as_uint(sa[3]),rb);
      sts64(so,sa[0],sa[1]);
      if(g<2) sts64(so+8*SROW*4,sa[2],sa[3]);
      bar_arrive(6,256);
      __syncwarp();
      if(lane==0) mbar_arrive(sb+SM_BAR+8*B_S);
    }
    TS(5);
    if(!last && !(F && g<3)) bar_sync(6,256);
    if(!last){
      #pragma unroll
      for(int u=0;u<NB1;u++) lds128u(bk[u],wof+u*512);
    }
    if(last){
      if(F) bar_arrive(3,256);
      else { bar_sync(3,256); float pv[4]; lds128f(pv,l16+SM_RV+g*512);
        stsm2t(sb+SM_VM+par*1024+(2*g+((lane>>3)&1))*128+(lane&7)*16,pack2(av[0]+pv[0],av[1]+pv[1]),pack2(av[2]+pv[2],av[3]+pv[3]));
        bar_arrive(5,160); }
      break;
    }
    uint32_t va1[4],va2[4],vx0,vx1;
    if(!F){
      mbar_wait_nt(sb+SM_BAR+8*(B_KV+par),(s>>1)&1);
      const int m=lane>>3;
      const uint32_t vb=sb+SM_KX+par*8192+4096+(2*g+(m&1))*128+(lane&7)*16;
      ldsm4t(va1,vb+(1+(m>>1))*1024);
      ldsm4t(va2,((m>>1)? (sb+SM_ZERO+(2*g+(m&1))*128+(lane&7)*16) : (vb+3*1024)));
      ldsm2t(vx0,vx1,vb);
    }
    TS(6);
    mbar_wait_nt(sb+SM_BAR+8*B_S,par);
    TS(7);
    {
      const uint32_t a0=sb+SM_S+(lane*SROW+warp)*4;
      float s0=lds32f(a0), s1=lds32f(a0+2048);
      float t0s=0.f,t1s=0.f;
      if(lane<8){ t0s=lds32f(a0+32*SROW*4); t1s=lds32f(a0+32*SROW*4+2048);}
      const float scale=0.08838834764831845f;
      uint32_t w2=pack2(s0+s1,t0s+t1s);
      w2=pack2(bflo(w2)*scale,bfhi(w2)*scale);
      const float x=bflo(w2); float y=bfhi(w2);
      if(lane>=8) y=-INFINITY;
      float mx=fmaxf(x,y);
      int im=__float_as_int(mx); im=(im>=0)?im:(im^0x7fffffff);
      im=__reduce_max_sync(0xffffffffu,im);
      im=(im>=0)?im:(im^0x7fffffff);
      mx=__int_as_float(im);
      const float L2E=1.4426950408889634f;
      float ex,ey;
      asm("ex2.approx.ftz.f32 %0,%1;":"=f"(ex):"f"((x-mx)*L2E));
      asm("ex2.approx.ftz.f32 %0,%1;":"=f"(ey):"f"((y-mx)*L2E));
      const uint32_t pb=pack2(ex,ey);
      const uint32_t pa=sb+SM_P+warp*16+(lane&7)*2;
      asm volatile("st.shared.u16 [%0],%1;"::"r"(pa+(lane>>3)*128),"h"((uint16_t)(pb&0xffff)):"memory");
      if(lane<8) asm volatile("st.shared.u16 [%0],%1;"::"r"(pa+4*128),"h"((uint16_t)(pb>>16)):"memory");
    }
    TS(8);
    if(F){
      bar_arrive(3,256);
      bar_sync(9,256);
      #pragma unroll
      for(int u=NB1;u<16;u++) lds128u(bk[u],wof+u*512);
    } else {
      bar_sync(3,256);
      uint32_t pb[4],pc0,pc1; float pv[4];
      ldsm4(pb,l16+SM_P); ldsm2(pc0,pc1,sb+SM_P+512+(lane&15)*16);
      lds128f(pv,l16+SM_RV+g*512);
      float o0[4]={0,0,0,0},o1[4]={0,0,0,0},o2[4]={0,0,0,0},ls[4]={0,0,0,0},lt[4]={0,0,0,0};
      const uint32_t ones[4]={0x3f803f80u,0x3f803f80u,0x3f803f80u,0x3f803f80u};
      mma16816(ls,ones,pb[0],pb[1]); mma16816(o1,va1,pb[2],pb[3]); mma16816(lt,ones,pc0,pc1); mma16816(o2,va2,pc0,pc1);
      uint32_t va0[4]; va0[0]=pack2(av[0]+pv[0],av[1]+pv[1]); va0[1]=pack2(av[2]+pv[2],av[3]+pv[3]); va0[2]=vx0; va0[3]=vx1;
      mma16816(o0,va0,pb[0],pb[1]); mma16816(ls,ones,pb[2],pb[3]);
      const float i0=__fdividef(1.f,ls[0]+lt[0]), i1=__fdividef(1.f,ls[1]+lt[1]);
      uint32_t w0=movt(pack2(((o0[0]+o1[0])+o2[0])*i0,((o0[1]+o1[1])+o2[1])*i1)), w1=movt(pack2(((o0[2]+o1[2])+o2[2])*i0,((o0[3]+o1[3])+o2[3])*i1));
      #pragma unroll
      for(int i=0;i<8;i++){
        uint32_t d=(r+i)&7;
        uint32_t ra=mapa(l4+SM_O+i*1024+g*256,d), rb=mapa(sb+SM_BAR+8*(B_O+i),d);
        st_async4(ra,w0,rb); st_async4(ra+128,w1,rb);
      }
      bar_arrive(9,256);
      TS(9);
      #pragma unroll
      for(int u=NB1;u<16;u++) lds128u(bk[u],wof+u*512);
      stsm2t(sb+SM_VM+par*1024+(2*g+((lane>>3)&1))*128+(lane&7)*16,va0[0],va0[1]);
      bar_arrive(5,160);
    }
    float ao[4][4];
    {
      #pragma unroll
      for(int q=0;q<4;q++){ao[0][q]=ao[1][q]=ao[2][q]=ao[3][q]=0.f;}
      uint32_t x0[4],x1[4],y0[4],y1[4];
      const uint32_t ob=l16+SM_O+slot0*1024, bb=sb+SM_BAR+8*(B_O+slot0);
      #define WO(i,b) { mma16816(ao[0],bk[i*4+0],b##0[0],b##0[1]); mma16816(ao[1],bk[i*4+1],b##0[2],b##0[3]); \
                        mma16816(ao[2],bk[i*4+2],b##1[0],b##1[1]); mma16816(ao[3],bk[i*4+3],b##1[2],b##1[3]); }
      mbar_wait_nt(bb,par);    LDB(x,ob,0)
      mbar_wait_nt(bb+8,par);  LDB(y,ob,1)  WO(0,x)
      mbar_wait_nt(bb+16,par); LDB(x,ob,2)  WO(1,y)
      mbar_wait_nt(bb+24,par); LDB(y,ob,3)  WO(2,x)
      WO(3,y)
    }
    const uint32_t ro=l16+SM_RO+g*512;
    if(F){
      #pragma unroll
      for(int q=0;q<4;q++) ao[0][q]=(ao[0][q]+ao[1][q])+(ao[2][q]+ao[3][q]);
      TS(10);
      sts128f(ro,ao[0]); bar_arrive(4,256);
      bar_sync(8,256); t0=clk32();
    } else {
      bar_sync(4,256);
      float po[4]; lds128f(po,ro);
      const uint32_t slot=s&1;
      const uint32_t tag=((wtags>>slot)+(s>>1))&1;
      uint32_t* pp=g_rpart+((slot*8+r)*8+c)*256+g*64+lane;
      float z[4];
      #pragma unroll
      for(int q=0;q<4;q++) z[q]=((ao[0][q]+ao[1][q])+(ao[2][q]+ao[3][q]))+po[q];
      TS(10);
      if(!(lane&4)){
        #pragma unroll
        for(int q=0;q<4;q++) z[q]=__uint_as_float((__float_as_uint(z[q])+0x10000u)&0xfffe0000u); }
      uint32_t w0=movt(pack2(z[0],z[1])), w1=movt(pack2(z[2],z[3]));
      stg_rlx(pp,w0|tag); stg_rlx(pp+32,w1|tag);
      t0=clk32();
      bar_arrive(8,256);
    }
    TS(11);
  }
}

__device__ __noinline__ void tail_path(const RP& P,uint8_t* smem,const uint32_t sb,const int tid,const unsigned E){
  const int lane=tid&31, warp=tid>>5, cta=blockIdx.x;
  float* xs=(float*)(smem+SM_MEM);
  float* red=(float*)(smem+SM_KX);
  int* sel=(int*)(smem+SM_Q);
  float* actb=(float*)(smem+SM_WOF+32768);
  const uint32_t w1=sb+SM_WVF, w2=sb+SM_WOF;
  { const int slot=tid&7, oct=cta+64*(slot>>1); const bf16* wsrc=(slot&1)? P.wup:P.wgate;
    if(slot<6&&oct<172){
      #pragma unroll 1
      for(int k=tid>>3;k<512;k+=32) cp16(w1+(k*8+slot)*16,wsrc+(size_t)k*1376+oct*8); }
    #pragma unroll 1
    for(int k=tid;k<1376;k+=256) cp16(w2+k*16,P.wdown+(size_t)k*512+cta*8);
    asm volatile("cp.async.commit_group;":::"memory"); }
  #pragma unroll 1
  for(int pass=0;pass<2;pass++){
    if(pass==1){ if(tid==0) wait_ge(&g_cnt[C_FIN*32],E*256+256); }
    asm volatile("cp.async.wait_group 0;":::"memory");
    bar_sync(10,256);
    float b1=-INFINITY,b2=-INFINITY; int i1=0x7fffffff,i2=0x7fffffff;
    { const float4 r0=__ldcg((const float4*)(g_r+tid*8)), r1=__ldcg((const float4*)(g_r+tid*8+4));
      float rv[8]={r0.x,r0.y,r0.z,r0.w,r1.x,r1.y,r1.z,r1.w};
      #pragma unroll
      for(int q=0;q<8;q++){ const float v=rv[q]; const int t=tid*8+q;
        if(v>b1){ b2=b1;i2=i1;b1=v;i1=t; } else if(v>b2){ b2=v;i2=t; } } }
    #pragma unroll 1
    for(int o=16;o;o>>=1){
      const float c1=__shfl_xor_sync(0xffffffffu,b1,o), c2=__shfl_xor_sync(0xffffffffu,b2,o);
      const int j1=__shfl_xor_sync(0xffffffffu,i1,o), j2=__shfl_xor_sync(0xffffffffu,i2,o);
      if(c1>b1||(c1==b1&&j1<i1)){ if(b1>c2||(b1==c2&&i1<j2)){ b2=b1;i2=i1; } else { b2=c2;i2=j2; } b1=c1;i1=j1; }
      else if(c1>b2||(c1==b2&&j1<i2)){ b2=c1;i2=j1; }
    }
    if(lane==0){ red[warp*4]=b1; red[warp*4+1]=b2; red[warp*4+2]=__int_as_float(i1); red[warp*4+3]=__int_as_float(i2); }
    bar_sync(10,256);
    if(warp==0){
      b1=-INFINITY;b2=-INFINITY;i1=0x7fffffff;i2=0x7fffffff;
      if(lane<16){ b1=red[(lane>>1)*4+(lane&1)]; i1=__float_as_int(red[(lane>>1)*4+2+(lane&1)]); }
      #pragma unroll 1
      for(int o=16;o;o>>=1){
        const float c1=__shfl_xor_sync(0xffffffffu,b1,o), c2=__shfl_xor_sync(0xffffffffu,b2,o);
        const int j1=__shfl_xor_sync(0xffffffffu,i1,o), j2=__shfl_xor_sync(0xffffffffu,i2,o);
        if(c1>b1||(c1==b1&&j1<i1)){ if(b1>c2||(b1==c2&&i1<j2)){ b2=b1;i2=i1; } else { b2=c2;i2=j2; } b1=c1;i1=j1; }
        else if(c1>b2||(c1==b2&&j1<i2)){ b2=c1;i2=j1; }
      }
      if(lane==0){ sel[0]=min(i1,2047); sel[1]=min(i2,2047); if(pass&&cta==0){ g_sel[0]=i1; g_sel[1]=i2; } }
    }
    bar_sync(10,256);
    const int t0=sel[0], t1=sel[1];
    { const uint32_t wa=__ldcg((const uint32_t*)(g_h2+(size_t)t0*512)+tid), wb=__ldcg((const uint32_t*)(g_h2+(size_t)t1*512)+tid);
      xs[2*tid]=bflo(wa); xs[2*tid+1]=bfhi(wa); xs[512+2*tid]=bflo(wb); xs[512+2*tid+1]=bfhi(wb); }
    bar_sync(10,256);
    float acc[2][8];
    #pragma unroll
    for(int q=0;q<8;q++){acc[0][q]=0.f;acc[1][q]=0.f;}
    #pragma unroll 1
    for(int k=tid>>3;k<512;k+=32){
      uint32_t wv[4]; lds128u(wv,w1+(k*8+(tid&7))*16); const float x0=xs[k], x1=xs[512+k];
      #pragma unroll
      for(int q=0;q<4;q++){ acc[0][2*q]+=x0*bflo(wv[q]); acc[0][2*q+1]+=x0*bfhi(wv[q]); acc[1][2*q]+=x1*bflo(wv[q]); acc[1][2*q+1]+=x1*bfhi(wv[q]); }
    }
    #pragma unroll
    for(int a=0;a<2;a++)
      #pragma unroll
      for(int q=0;q<8;q++){ float v=acc[a][q]; v+=__shfl_xor_sync(0xffffffffu,v,8); v+=__shfl_xor_sync(0xffffffffu,v,16); if(lane<8) red[64+(warp*8+lane)*16+a*8+q]=v; }
    bar_sync(10,256);
    if(tid<48){ const int o3=tid>>4, a=(tid>>3)&1, q=tid&7, oct=cta+64*o3;
      float gs=0.f,us=0.f;
      #pragma unroll 1
      for(int w=0;w<8;w++){ gs+=red[64+(w*8+2*o3)*16+a*8+q]; us+=red[64+(w*8+2*o3+1)*16+a*8+q]; }
      gs=bf16r(gs); us=bf16r(us);
      const float sg=bf16r(__fdividef(gs,1.f+__expf(-gs)));
      if(pass&&oct<172) g_act[a*1376+oct*8+q]=bf16r(sg*us); }
    bar_sync(10,256);
    float f_rv=0.f,f_h2=0.f,f_x1=0.f,f_gb=0.f;
    if(tid<16){ const int t=(tid>>3)? t1:t0, dcol=8*cta+(tid&7);
      f_rv=__ldcg(g_r+t); f_h2=__bfloat162float(__ldcg(g_h2+(size_t)t*512+dcol)); f_x1=__bfloat162float(__ldcg(g_x1+(size_t)t*512+dcol)); f_gb=__bfloat162float(__ldcg(g_mod+2560+dcol)); }
    if(pass&&tid==0){ red_rel(&g_cnt[C_ACT*32],1u); wait_ge(&g_cnt[C_ACT*32],E*64+64); }
    bar_sync(10,256);
    { float av[11];
      #pragma unroll
      for(int q=0;q<11;q++){ const int k=tid+256*q; av[q]=(k<2752)? __ldcg(g_act+k):0.f; }
      #pragma unroll
      for(int q=0;q<11;q++){ const int k=tid+256*q; if(k<2752) actb[k]=av[q]; } }
    bar_sync(10,256);
    #pragma unroll
    for(int q=0;q<8;q++){acc[0][q]=0.f;acc[1][q]=0.f;}
    #pragma unroll 1
    for(int k=tid;k<1376;k+=256){
      uint32_t wv[4]; lds128u(wv,w2+k*16); const float a0=actb[k], a1=actb[1376+k];
      #pragma unroll
      for(int q=0;q<4;q++){ acc[0][2*q]+=a0*bflo(wv[q]); acc[0][2*q+1]+=a0*bfhi(wv[q]); acc[1][2*q]+=a1*bflo(wv[q]); acc[1][2*q+1]+=a1*bfhi(wv[q]); }
    }
    #pragma unroll 1
    for(int o=16;o;o>>=1){
      #pragma unroll
      for(int q=0;q<8;q++){ acc[0][q]+=__shfl_xor_sync(0xffffffffu,acc[0][q],o); acc[1][q]+=__shfl_xor_sync(0xffffffffu,acc[1][q],o); } }
    if(lane==0){
      #pragma unroll
      for(int q=0;q<8;q++){ red[2048+warp*16+q]=acc[0][q]; red[2048+warp*16+8+q]=acc[1][q]; } }
    bar_sync(10,256);
    if(tid<16){ const int a=tid>>3, q=tid&7; float y=0.f;
      #pragma unroll 1
      for(int w=0;w<8;w++) y+=red[2048+w*16+a*8+q];
      const int t=a? t1:t0, dcol=8*cta+q;
      const float rs=bf16r(__fdividef(1.f,1.f+__expf(-f_rv)));
      y=bf16r(bf16r(y)*rs);
      const float hp=bf16r(f_h2+y);
      const bf16 res=__float2bfloat16_rn(f_x1+bf16r(f_gb*hp));
      if(pass) P.out[(size_t)t*512+dcol]=res; }
    bar_sync(10,256);
  }
  if(tid==0) launch_done(E,P.ng+64);
}

__global__ void __launch_bounds__(384,1) rkernel(const __grid_constant__ RP P){
  extern __shared__ __align__(1024) uint8_t smem[];
  const uint32_t sb=s2u(smem);
  const int tid=threadIdx.x; const int lane=__shfl_sync(0xffffffffu,tid&31,tid&31);
  const int warp=__shfl_sync(0xffffffffu,tid>>5,0);
  uint32_t r; asm("mov.u32 %0,%%cluster_ctarank;":"=r"(r));
  const int c=blockIdx.x>>3;
  const unsigned E=*(volatile unsigned*)&g_epoch;
  asm volatile("griddepcontrol.launch_dependents;":::"memory");

  if(tid==0){
    for(int i=0;i<8;i++){ mbar_init(sb+SM_BAR+8*(B_MEM+i),1); mbar_init(sb+SM_BAR+8*(B_O+i),1);}
    mbar_init(sb+SM_BAR+8*B_W,1); mbar_init(sb+SM_BAR+8*B_S,4); mbar_init(sb+SM_BAR+8*B_KV,1); mbar_init(sb+SM_BAR+8*(B_KV+1),1);
    asm volatile("fence.mbarrier_init.release.cluster;":::"memory");
    for(int i=0;i<8;i++){ mbar_expect(sb+SM_BAR+8*(B_MEM+i),1024); mbar_expect(sb+SM_BAR+8*(B_O+i),1024);}
    mbar_expect(sb+SM_BAR+8*B_S,1280);
    sts32(sb+SM_BAR+8*31,0);
  }
  if(tid<256){ ((uint32_t*)(smem+SM_ZERO))[tid]=0; ((uint32_t*)(smem+SM_P))[tid]=0; }
  __syncthreads();

  if(warp>=8){
    asm volatile("setmaxnreg.dec.sync.aligned.u32 " STR(HREG) ";");
    if(warp>9) return;
    if(warp==9){
      asm volatile("barrier.cluster.arrive.release.aligned;\nbarrier.cluster.wait.acquire.aligned;":::"memory");
      int n=0; while(lds32(sb+SM_BAR+8*31)==0){ __nanosleep(2000); if(++n>20000) asm volatile("trap;"); }
      return;
    }
    const int h=4*c+(r>>1), j=r&1;
    bar_sync(15,288);
    if(lane==0){
      mbar_expect(sb+SM_BAR+8*B_W,131072);
      for(int q=0;q<8;q++){ tma2d(sb+SM_WVF+q*8192,&P.mq,h*128+64*j,q*64,sb+SM_BAR+8*B_W); tma2d(sb+SM_WOF+q*8192,&P.mk,h*128+64*j,q*64,sb+SM_BAR+8*B_W); }
    }
    __syncwarp();
    bar_sync(13,288);
    if(lane==0){
      fence_async();
      mbar_expect(sb+SM_BAR+8*B_W,131072);
      for(int q=0;q<8;q++){ tma2d(sb+SM_WVF+q*8192,&P.mv,h*128+64*j,q*64,sb+SM_BAR+8*B_W); tma2d(sb+SM_WOF+q*8192,&P.mo,64*r,c*512+q*64,sb+SM_BAR+8*B_W); }
    }
    __syncwarp();
    asm volatile("barrier.cluster.arrive.release.aligned;\nbarrier.cluster.wait.acquire.aligned;":::"memory");
    if(lane==0){
      wait_ge(&g_cnt[C_KV*32],E*32+32); fence_async();
      mbar_expect(sb+SM_BAR+8*B_KV,8192);
      bulk_g2s(sb+SM_KX,g_kvx+((size_t)(0*32+h)*2+j)*4096,8192,sb+SM_BAR+8*B_KV);
    }
    __syncwarp();
    #pragma unroll 1
    for(int s=0;s<NSEG;s++){
      const uint32_t par=s&1;
      if(lane<8){ uint32_t b=sb+SM_BAR+8*(B_MEM+lane); mbar_wait(b,par); mbar_expect(b,1024);}
      __syncwarp();
      if(s<NSEG-2 && lane==0){
        if(((s+1)&3)==0){ wait_ge(&g_cnt[(C_KV+((s+1)>>2))*32],E*32+32); fence_async(); }
        uint32_t b=sb+SM_BAR+8*(B_KV+((s+1)&1));
        mbar_expect(b,8192);
        asm volatile("cp.async.bulk.shared::cluster.global.mbarrier::complete_tx::bytes [%0],[%1],%2,[%3];"::"r"(sb+SM_KX+((s+1)&1)*8192),"l"(g_kvx+((size_t)((s+1)*32+h)*2+j)*4096),"r"(8192),"r"(b):"memory");
      }
      __syncwarp();
      bar_sync(5,160);
      uint8_t* dst=(uint8_t*)g_kvm+(((size_t)s*32+h)*2+j)*2048+lane*16;
      #pragma unroll
      for(int q=0;q<4;q++){
        uint32_t src=sb+((q<2)? (SM_KM+par*1024+q*512):(SM_VM+par*1024+(q-2)*512))+lane*16;
        uint32_t v[4]; lds128u(v,src);
        *(uint4*)(dst+q*512)=make_uint4(v[0],v[1],v[2],v[3]);
      }
      __syncwarp();
      if(lane==0){ asm volatile("st.release.gpu.global.b32 [%0],%1;"::"l"(&g_prog[(h*2+j)*32]),"r"(E*64+s+1):"memory"); }
      if(s<NSEG-1){
        if(lane<9){ uint32_t b=sb+SM_BAR+8*(B_O+lane); mbar_wait(b,par); mbar_expect(b,lane==8?1280:1024);}
      }
      __syncwarp();
    }
    bar_sync(14,288);
  } else {
    asm volatile("setmaxnreg.inc.sync.aligned.u32 " STR(CREG) ";");
    if(warp>=4) compute_path<1>(P,smem+SM_RQK,sb,warp,lane,r,c,E); else compute_path<0>(P,smem+SM_RQK,sb,warp,lane,r,c,E);
    bar_sync(14,288);
    tail_path(P,smem,sb,tid,E);
  }
  if(tid==0) sts32(sb+SM_BAR+8*31,1);
  asm volatile("barrier.cluster.arrive.release.aligned;\nbarrier.cluster.wait.acquire.aligned;":::"memory");
}
typedef CUresult (*PFN_encodeTiled)(CUtensorMap*,CUtensorMapDataType,cuuint32_t,void*,const cuuint64_t*,const cuuint64_t*,const cuuint32_t*,const cuuint32_t*,CUtensorMapInterleave,CUtensorMapSwizzle,CUtensorMapL2promotion,CUtensorMapFloatOOBfill);
static void make_map(PFN_encodeTiled fn,CUtensorMap* m,const void* ptr,uint64_t ncols,uint64_t nrows){
  cuuint64_t dims[2]={ncols,nrows}; cuuint64_t strides[1]={ncols*2}; cuuint32_t box[2]={64,64}; cuuint32_t es[2]={1,1};
  fn(m,CU_TENSOR_MAP_DATA_TYPE_BFLOAT16,2,(void*)ptr,dims,strides,box,es,CU_TENSOR_MAP_INTERLEAVE_NONE,CU_TENSOR_MAP_SWIZZLE_128B,CU_TENSOR_MAP_L2_PROMOTION_L2_256B,CU_TENSOR_MAP_FLOAT_OOB_FILL_NONE);
}
#define R_DELAY 200
#define R_PERIOD 200
extern "C" void kernel_launch(void* const* d_in, const int* in_sizes, int n_in, void* d_out, int out_size){
  (void)in_sizes;(void)n_in;(void)out_size;
  static PFN_encodeTiled enc=nullptr; static int nsm=0;
  if(!enc){
    void* fn=nullptr; cudaDriverEntryPointQueryResult qr;
    cudaGetDriverEntryPoint("cuTensorMapEncodeTiled",&fn,cudaEnableDefault,&qr);
    enc=(PFN_encodeTiled)fn;
    cudaFuncSetAttribute(rkernel,cudaFuncAttributeMaxDynamicSharedMemorySize,SM_TOTAL);
    cudaFuncSetAttribute(gkernel,cudaFuncAttributeMaxDynamicSharedMemorySize,GS_TOTAL);
    int dev=0; cudaGetDevice(&dev); cudaDeviceGetAttribute(&nsm,cudaDevAttrMultiProcessorCount,dev);
  }
  const bf16* x=(const bf16*)d_in[0]; const bf16* mem0=(const bf16*)d_in[1];
  const bf16* Wq=(const bf16*)d_in[2]; const bf16* Wk=(const bf16*)d_in[3]; const bf16* Wv=(const bf16*)d_in[4]; const bf16* Wo=(const bf16*)d_in[5];
  GP gp;
  make_map(enc,&gp.mq,Wq,4096,512); make_map(enc,&gp.mk,Wk,4096,512); make_map(enc,&gp.mv,Wv,4096,512); make_map(enc,&gp.mo,Wo,512,4096);
  gp.x=x; gp.wr=(const bf16*)d_in[8]; gp.wgate=(const bf16*)d_in[9]; gp.wup=(const bf16*)d_in[10]; gp.wdown=(const bf16*)d_in[11];
  gp.c=(const bf16*)d_in[12]; gp.wmod=(const bf16*)d_in[13]; gp.out=(bf16*)d_out;
  RP rp; rp.mem0=mem0; rp.Wq=Wq; rp.Wk=Wk; rp.Wv=Wv; rp.Wo=Wo; rp.x=x; rp.c=gp.c; rp.wmod=gp.wmod;
  rp.mq=gp.mq; rp.mk=gp.mk; rp.mv=gp.mv; rp.mo=gp.mo; rp.delay=R_DELAY; rp.period=R_PERIOD;
  rp.wgate=gp.wgate; rp.wup=gp.wup; rp.wdown=gp.wdown; rp.out=gp.out; rp.ng=(nsm-64<1)?1:nsm-64;
  cudaStream_t st=cudaStreamPerThread;
  { cudaLaunchConfig_t cfg={}; cfg.gridDim=dim3(64); cfg.blockDim=dim3(384); cfg.dynamicSmemBytes=SM_TOTAL; cfg.stream=st;
    cudaLaunchAttribute at[1]; at[0].id=cudaLaunchAttributeClusterDimension; at[0].val.clusterDim.x=8; at[0].val.clusterDim.y=1; at[0].val.clusterDim.z=1; cfg.attrs=at; cfg.numAttrs=1;
    cudaLaunchKernelEx(&cfg,rkernel,rp); }
  { int ng=nsm-64; if(ng<1) ng=1;
    cudaLaunchConfig_t cfg={}; cfg.gridDim=dim3(ng); cfg.blockDim=dim3(384); cfg.dynamicSmemBytes=GS_TOTAL; cfg.stream=st;
    cudaLaunchAttribute at[1]; at[0].id=cudaLaunchAttributeProgrammaticStreamSerialization; at[0].val.programmaticStreamSerializationAllowed=1; cfg.attrs=at; cfg.numAttrs=1;
    cudaLaunchKernelEx(&cfg,gkernel,gp); }
}
```
